```python
import torch

def _softmax(x, axis=-1):
    return torch.softmax(x, dim=axis)
def _gelu(x):
    return torch.nn.functional.gelu(x, approximate="tanh")
def _silu(x):
    return torch.nn.functional.silu(x)
def _sigmoid(x):
    return torch.sigmoid(x)
def _layernorm(x, axis=-1, eps=1e-5):
    m = x.mean(dim=axis, keepdim=True)
    v = x.var(dim=axis, keepdim=True, unbiased=False)
    return (x - m) / torch.sqrt(v + eps)
def _scatter_add(tgt, idx, src, axis=0):
    return tgt.clone().index_add_(axis, idx, src)
def _segment_sum(src, seg, n):
    out = torch.zeros((n,) + src.shape[1:], dtype=src.dtype)
    return out.index_add_(0, seg, src)
def _pad(x, pw):
    flat = tuple(v for pair in reversed(pw) for v in pair)
    return torch.nn.functional.pad(x, flat)

kernel_name = 'standalone__gqa_block_cached__decode'

def setup_inputs():

    _w = (lambda a: (lambda t: t.to(torch.bfloat16) if t.is_floating_point() else t)(torch.as_tensor(a)))
    B, Sq, D = 1, 1, 640
    Hq, Hkv, Sk, Dh = 32, 32, 8192, 192
    assert Hq % Hkv == 0, (Hq, Hkv)
    return {
        "x": _w((lambda *s: torch.randn(*s, dtype=torch.bfloat16) * 0.8)(B, Sq, D)),
        "k_cache": _w((lambda *s: torch.randn(*s, dtype=torch.bfloat16) * 0.8)(B, Hkv, Sk, Dh)),
        "v_cache": _w((lambda *s: torch.randn(*s, dtype=torch.bfloat16) * 0.05)(B, Hkv, Sk, Dh)),
        "wq": _w((lambda *s: torch.randn(*s, dtype=torch.bfloat16) * 0.8)(D, Hq * Dh) * (D ** -0.5)),
        "wo": _w((lambda *s: torch.randn(*s, dtype=torch.bfloat16) * 0.05)(Hq * Dh, D) * ((Hq * Dh) ** -0.5)),
    }

def reference(x, k_cache, v_cache, wq, wo):
    B, Sq, D = x.shape
    Hq, Dh = 32, 192
    Hkv = k_cache.shape[1]
    rep = Hq // Hkv
    q = (lambda x, *d: x.permute(*d))((x @ wq).reshape(B, Sq, Hq, Dh), 0, 2, 1, 3)
    k = (lambda x, n, axis: torch.repeat_interleave(x, n, dim=axis))(k_cache, rep, axis=1)
    v = (lambda x, n, axis: torch.repeat_interleave(x, n, dim=axis))(v_cache, rep, axis=1)
    scores = torch.einsum("bhqd,bhkd->bhqk", q, k) * (Dh ** -0.5)
    p = _softmax(scores, axis=-1)
    o = torch.einsum("bhqk,bhkd->bhqd", p, v)
    return (lambda x, *d: x.permute(*d))(o, 0, 2, 1, 3).reshape(B, Sq, Hq * Dh) @ wo
```

```cpp
#include <cuda_runtime.h>
#include <cuda_bf16.h>
#include <cuda.h>
#include <stdint.h>

namespace {

constexpr int D_MODEL = 640, NH = 32, SK = 8192, DH = 192;
constexpr int NSPLIT = 4, NCTA = NH * NSPLIT;
constexpr int KEYS = SK / NSPLIT;
constexpr int CH_KEYS = 32;
constexpr int NCH = KEYS / CH_KEYS;
constexpr int CH_BYTES = CH_KEYS * DH * 2;
constexpr int NSLOT = 16;
constexpr int QROWS = D_MODEL / NSPLIT;
constexpr int OROWS = DH / NSPLIT;
constexpr int WQ_PIECES = QROWS / CH_KEYS;
constexpr int WO_PIECES = OROWS / 8;
constexpr int WO_PIECE_BYTES = 8 * D_MODEL * 2;
constexpr int N_K = WQ_PIECES, N_V = N_K + NCH, N_WO = N_V + NCH;
static_assert(N_WO % NSLOT + WO_PIECES <= NSLOT, "wo pieces sit in consecutive slots");
constexpr int NTHREADS = 320;

#define PACE_EFF 0.975
#define PACE_OFF -100
#define KV_RUN 4
#define PF_WQ 96
#define L_TAIL 3
#define Q_DELAY 700
#define O_DELAY 900

constexpr int OFF_RING = 0;
constexpr int OFF_S = OFF_RING + NSLOT * CH_BYTES;
constexpr int OFF_Q = OFF_S + KEYS * 4;
constexpr int OFF_O = OFF_Q + DH * 2;
constexpr int OFF_X = OFF_O + 128;
constexpr int OFF_RED = OFF_X + QROWS * 2;
constexpr int OFF_BAR = OFF_RED + 48;
constexpr int NBAR = 2 * NSLOT + WO_PIECES + 3;
constexpr int SMEM_BYTES = OFF_BAR + NBAR * 8 + 1024;

constexpr unsigned SPIN_LIMIT = 1u << 24;

struct __align__(16384) HeadBox {
    uint32_t epoch, pad[31];
    uint32_t ml[2][32];
    uint32_t q[2][NSPLIT][DH];
    uint32_t o[2][NSPLIT][NSPLIT][64];
};
__device__ HeadBox g_box[NH];
__device__ __align__(32768) float4 g_acc[NCTA][2][8];

#define TS(k)
#define TC(n)
#define PROF_END()

__device__ __forceinline__ uint32_t smem_u32(const void* p) { return (uint32_t)__cvta_generic_to_shared(p); }
__device__ __forceinline__ void mbar_init(uint32_t a, uint32_t c) { asm volatile("mbarrier.init.shared::cta.b64 [%0], %1;" ::"r"(a), "r"(c) : "memory"); }
__device__ __forceinline__ void mbar_expect_tx(uint32_t a, uint32_t b) { asm volatile("mbarrier.arrive.expect_tx.shared::cta.b64 _, [%0], %1;" ::"r"(a), "r"(b) : "memory"); }
__device__ __forceinline__ void mbar_arrive(uint32_t a, uint32_t n) { asm volatile("mbarrier.arrive.shared::cta.b64 _, [%0], %1;" ::"r"(a), "r"(n) : "memory"); }
__device__ __forceinline__ void mbar_wait(uint32_t a, uint32_t parity) {
    uint32_t done;
    unsigned it = 0;
    do {
        asm volatile("{\n.reg .pred p;\nmbarrier.try_wait.parity.shared::cta.b64 p, [%1], %2;\nselp.u32 %0, 1, 0, p;\n}"
                     : "=r"(done) : "r"(a), "r"(parity) : "memory");
        if (++it > SPIN_LIMIT) __trap();
    } while (!done);
}
__device__ __forceinline__ uint32_t gtime_lo() { uint32_t t; asm volatile("mov.u32 %0, %globaltimer_lo;" : "=r"(t)); return t; }
__device__ __forceinline__ void wait_until(uint32_t due) {
    for (int it = 0; it < 4096 && (int)(gtime_lo() - due) < 0; it++) {}
}
__device__ __forceinline__ void bar_sync(int id, int n) { asm volatile("bar.sync %0, %1;" ::"r"(id), "r"(n) : "memory"); }
__device__ __forceinline__ void tma_3d(uint32_t dst, const CUtensorMap* tm, int c1, int c2, uint32_t mbar, uint64_t pol) {
    asm volatile("cp.async.bulk.tensor.3d.shared::cluster.global.mbarrier::complete_tx::bytes.L2::cache_hint [%0], [%1, {%3, %4, %5}], [%2], %6;"
                 ::"r"(dst), "l"(tm), "r"(mbar), "r"(0), "r"(c1), "r"(c2), "l"(pol) : "memory");
}
__device__ __forceinline__ void ldsm4(uint32_t (&r)[4], uint32_t a) {
    asm volatile("ldmatrix.sync.aligned.m8n8.x4.shared.b16 {%0,%1,%2,%3}, [%4];" : "=r"(r[0]), "=r"(r[1]), "=r"(r[2]), "=r"(r[3]) : "r"(a) : "memory");
}
__device__ __forceinline__ void ldsm4t(uint32_t (&r)[4], uint32_t a) {
    asm volatile("ldmatrix.sync.aligned.m8n8.x4.trans.shared.b16 {%0,%1,%2,%3}, [%4];" : "=r"(r[0]), "=r"(r[1]), "=r"(r[2]), "=r"(r[3]) : "r"(a) : "memory");
}
__device__ __forceinline__ void mma_bf16(float (&c)[4], const uint32_t (&a)[4], uint32_t b0, uint32_t b1) {
    asm volatile("mma.sync.aligned.m16n8k16.row.col.f32.bf16.bf16.f32 {%0,%1,%2,%3}, {%4,%5,%6,%7}, {%8,%9}, {%0,%1,%2,%3};"
                 : "+f"(c[0]), "+f"(c[1]), "+f"(c[2]), "+f"(c[3])
                 : "r"(a[0]), "r"(a[1]), "r"(a[2]), "r"(a[3]), "r"(b0), "r"(b1));
}
__device__ __forceinline__ void mma_bf16_k8(float (&c)[4], uint32_t a0, uint32_t a1, uint32_t b0) {
    asm volatile("mma.sync.aligned.m16n8k8.row.col.f32.bf16.bf16.f32 {%0,%1,%2,%3}, {%4,%5}, {%6}, {%0,%1,%2,%3};"
                 : "+f"(c[0]), "+f"(c[1]), "+f"(c[2]), "+f"(c[3]) : "r"(a0), "r"(a1), "r"(b0));
}
__device__ __forceinline__ uint2 ld_box2(const uint32_t* p) {
    uint2 v;
    asm volatile("ld.relaxed.gpu.global.v2.u32 {%0,%1}, [%2];" : "=r"(v.x), "=r"(v.y) : "l"(p) : "memory");
    return v;
}
__device__ __forceinline__ void st_box(uint32_t* p, uint32_t v) { asm volatile("st.relaxed.gpu.global.u32 [%0], %1;" ::"l"(p), "r"(v) : "memory"); }
__device__ __forceinline__ void st_box2(uint32_t* p, uint32_t a, uint32_t b) {
    asm volatile("st.relaxed.gpu.global.v2.u32 [%0], {%1,%2};" ::"l"(p), "r"(a), "r"(b) : "memory");
}
__device__ __forceinline__ void st_zero16(void* p) {
    asm volatile("st.relaxed.gpu.global.v4.u32 [%0], {%1,%1,%1,%1};" ::"l"(p), "r"(0) : "memory");
}
__device__ __forceinline__ void poll4(uint2 (&v)[NSPLIT], const uint32_t* p, int stride) {
    unsigned it = 0;
    while (true) {
        bool ok = true;
#pragma unroll
        for (int r = 0; r < NSPLIT; r++) v[r] = ld_box2(p + r * stride);
#pragma unroll
        for (int r = 0; r < NSPLIT; r++) ok = ok && v[r].x != 0 && v[r].y != 0;
        if (__all_sync(~0u, ok)) break;
        if (++it > SPIN_LIMIT) __trap();
    }
}
__device__ __forceinline__ uint32_t enc(float v) { uint32_t e = ~__float_as_uint(v); return e ? e : 0x80000000u; }
__device__ __forceinline__ float dec(uint32_t e) { return __uint_as_float(~e); }
__device__ __forceinline__ float bf_lo(uint32_t u) { return __uint_as_float(u << 16); }
__device__ __forceinline__ float bf_hi(uint32_t u) { return __uint_as_float(u & 0xffff0000u); }
__device__ __forceinline__ uint32_t pack_bf2(float lo, float hi) {
    uint32_t r;
    asm("cvt.rn.bf16x2.f32 %0, %1, %2;" : "=r"(r) : "f"(hi), "f"(lo));
    return r;
}

__device__ __forceinline__ void st_bf16(__nv_bfloat16* p, float v) {
    asm volatile("st.global.u16 [%0], %1;" ::"l"(p), "h"(__bfloat16_as_ushort(__float2bfloat16_rn(v))) : "memory");
}

__global__ void __launch_bounds__(NTHREADS, 1)
fused_decode_kernel(const __grid_constant__ CUtensorMap tmQ, const __grid_constant__ CUtensorMap tmK,
                    const __grid_constant__ CUtensorMap tmV, const __grid_constant__ CUtensorMap tmW,
                    const __nv_bfloat16* __restrict__ x, const __nv_bfloat16* __restrict__ wq,
                    __nv_bfloat16* __restrict__ out, HeadBox* boxes, float4 (*acc)[2][8], uint32_t tau_ps) {
    extern __shared__ uint8_t smem_raw[];
    const int tid = threadIdx.x, lane = tid & 31;
    const int cta = blockIdx.x, h = cta >> 2, j = cta & 3;
    const uint32_t t_start = gtime_lo();
    HeadBox& box = boxes[h];
    uint4 early;
    if (tid >= 288 && tid <= 288 + QROWS / 8) {
        const void* p = tid < 288 + QROWS / 8 ? (const void*)(x + j * QROWS + (tid - 288) * 8) : (const void*)&box.epoch;
        asm volatile("ld.relaxed.gpu.global.v4.u32 {%0,%1,%2,%3}, [%4];" : "=r"(early.x), "=r"(early.y), "=r"(early.z), "=r"(early.w) : "l"(p) : "memory");
    }
    if (tid < PF_WQ) {
        const char* p = (const char*)(wq + (size_t)(j * QROWS + tid) * (NH * DH) + h * DH);
        asm volatile("prefetch.global.L2 [%0];" ::"l"(p));
        asm volatile("prefetch.global.L2 [%0];" ::"l"(p + 128));
        asm volatile("prefetch.global.L2 [%0];" ::"l"(p + 256));
    }
    const uint32_t sraw = smem_u32(smem_raw);
    const uint32_t sb = (sraw + 1023u) & ~1023u;
    uint8_t* sp = smem_raw + (sb - sraw);
    const uint32_t bar_full = sb + OFF_BAR, bar_empty = bar_full + 8 * NSLOT, bar_wo = bar_empty + 8 * NSLOT;
    const uint32_t bar_o = bar_wo + 8 * WO_PIECES, bar_go = bar_o + 8, bar_sent = bar_go + 8;
    constexpr uint64_t pol = 0x12F0000000000000ull;
    if (tid == 256) {
        TS(0);
#pragma unroll
        for (int n = 0; n < WQ_PIECES; n++) mbar_init(bar_full + 8 * n, 1);
#pragma unroll 1
        for (int n = 0; n < WQ_PIECES; n++) {
            mbar_expect_tx(bar_full + 8 * n, CH_BYTES);
            tma_3d(sb + OFF_RING + n * CH_BYTES, &tmQ, 3 * h, j * QROWS + n * CH_KEYS, bar_full + 8 * n, pol);
        }
        asm volatile("prefetch.tensormap [%0];" ::"l"(&tmK) : "memory");
        TS(15);
#pragma unroll
        for (int n = WQ_PIECES; n < NSLOT; n++) mbar_init(bar_full + 8 * n, 1);
    }
    if (tid == 128) {
#pragma unroll
        for (int n = 0; n < NSLOT; n++) mbar_init(bar_empty + 8 * n, 4);
    }
    if (tid == 160) {
#pragma unroll
        for (int n = 0; n < WO_PIECES + 3; n++) mbar_init(bar_wo + 8 * n, n == WO_PIECES + 2 ? 4 : 1);
    }
    const int warp = __shfl_sync(~0u, tid >> 5, 0);
    volatile uint32_t* sEpoch = (volatile uint32_t*)(sp + OFF_X + QROWS * 2 + 32);
    if (tid >= 288 && tid <= 288 + QROWS / 8) *(uint4*)(tid < 288 + QROWS / 8 ? sp + OFF_X + (tid - 288) * 16 : (uint8_t*)sEpoch) = early;
    asm volatile("fence.mbarrier_init.release.cluster;" ::: "memory");
    __syncthreads();
    const uint32_t epoch = *sEpoch;
    const int par = epoch & 1;

    if (warp == 8) {
        if (lane == 0) {
            const uint32_t t0 = t_start + (uint32_t)(PACE_OFF);
            const int key0 = h * SK + j * KV_RUN * CH_KEYS;
#pragma unroll 1
            for (int n = N_K; n < N_WO; n++) {
                const int s = n & (NSLOT - 1), i = (n - N_K) & (NCH - 1);
                if (n == NSLOT) asm volatile("prefetch.tensormap [%0];" ::"l"(&tmV) : "memory");
                if (n == N_V) asm volatile("prefetch.tensormap [%0];" ::"l"(&tmW) : "memory");
                if (n >= NSLOT) mbar_wait(bar_empty + 8 * s, ((n / NSLOT) - 1) & 1);
                wait_until(t0 + (n - 1) * tau_ps / 1000u);
                mbar_expect_tx(bar_full + 8 * s, CH_BYTES);
                tma_3d(sb + OFF_RING + s * CH_BYTES, n < N_V ? &tmK : &tmV, 0,
                       key0 + (i / KV_RUN * (NSPLIT * KV_RUN) + i % KV_RUN) * CH_KEYS, bar_full + 8 * s, pol);
            }
            mbar_arrive(bar_go, 1);
#pragma unroll 1
            for (int p = 0; p < WO_PIECES; p++) {
                const int n = N_WO + p, s = n & (NSLOT - 1), w = n - L_TAIL;
                mbar_wait(bar_empty + 8 * s, ((n / NSLOT) - 1) & 1);
                if (w < N_WO) mbar_wait(bar_full + 8 * (w & (NSLOT - 1)), (w / NSLOT) & 1);
                else mbar_wait(bar_wo + 8 * (w - N_WO), 0);
                wait_until(t0 + ((N_WO - 1) * tau_ps + p * (tau_ps / 6 * 5)) / 1000u);
                mbar_expect_tx(bar_wo + 8 * p, WO_PIECE_BYTES);
                tma_3d(sb + OFF_RING + s * CH_BYTES, &tmW, h * DH + j * OROWS + 8 * p, 0, bar_wo + 8 * p, pol);
            }
            TS(1);
        }
        PROF_END();
        return;
    }

    if (warp == 9) {
        bar_sync(4, 160);
        st_zero16((uint4*)box.o[par ^ 1][j] + lane);
        st_zero16((uint4*)box.o[par ^ 1][j] + 32 + lane);
        st_zero16((uint4*)box.q[par ^ 1][j] + lane);
        if (lane < 16) st_zero16((uint4*)box.q[par ^ 1][j] + 32 + lane);
        if (lane == 0) st_box2(&box.ml[par ^ 1][2 * j], 0, 0);
        if (lane < 2) st_zero16(&acc[cta][par ^ 1][lane]);
        if (lane == 0 && j == 0) st_box(&box.epoch, epoch + 1);
        const int dl = min(lane, OROWS / 2 - 1);
        uint32_t* oi = &box.o[par][j][0][2 * dl];
        uint32_t oaddr = sb + OFF_O + dl * 4;
        asm volatile("" : "+l"(oi), "+r"(oaddr));
        uint2 v[NSPLIT];
        mbar_wait(bar_go, 0);
        poll4(v, box.ml[par], 2);
        const float M = fmaxf(fmaxf(dec(v[0].x), dec(v[1].x)), fmaxf(dec(v[2].x), dec(v[3].x)));
        float c0 = exp2f(dec(v[0].x) - M), c1 = exp2f(dec(v[1].x) - M), c2 = exp2f(dec(v[2].x) - M), c3 = exp2f(dec(v[3].x) - M);
        const float inv = 1.f / (fmaf(c0, dec(v[0].y), c1 * dec(v[1].y)) + fmaf(c2, dec(v[2].y), c3 * dec(v[3].y)));
        c0 *= inv; c1 *= inv; c2 *= inv; c3 *= inv;
        mbar_wait(bar_sent, 0);
        wait_until(gtime_lo() + O_DELAY);
        poll4(v, oi, 64);
        if (lane == 0) TS(13);
        const uint32_t o2 = pack_bf2(fmaf(c0, dec(v[0].x), c1 * dec(v[1].x)) + fmaf(c2, dec(v[2].x), c3 * dec(v[3].x)),
                                     fmaf(c0, dec(v[0].y), c1 * dec(v[1].y)) + fmaf(c2, dec(v[2].y), c3 * dec(v[3].y)));
        asm volatile("st.shared.u32 [%0], %1;" ::"r"(oaddr), "r"(o2) : "memory");
        __syncwarp();
        if (lane == 0) { mbar_arrive(bar_o, 1); TS(6); }
        PROF_END();
        return;
    }

    const int g = lane >> 2, t = lane & 3;
    if (warp < 4) {
        uint32_t voff[3];
        {
            const int row = (lane & 7) + (lane >> 4) * 8;
#pragma unroll
            for (int m = 0; m < 3; m++) {
                const int ch = 6 * warp + 2 * m + ((lane >> 3) & 1), L = 3 * row + (ch >> 3);
                voff[m] = L * 128 + (((ch & 7) ^ (L & 7)) << 4);
            }
        }
        {
            float qa[3][4];
#pragma unroll
            for (int m = 0; m < 3; m++) qa[m][0] = qa[m][1] = qa[m][2] = qa[m][3] = 0.f;
#pragma unroll 1
            for (int n = 0; n < WQ_PIECES; n++) {
                const uint32_t* xs = (const uint32_t*)(sp + OFF_X) + 16 * n + t;
                const uint32_t xb[4] = {xs[0], xs[4], xs[8], xs[12]};
                mbar_wait(bar_full + 8 * n, 0);
#pragma unroll
                for (int ks = 0; ks < 2; ks++)
#pragma unroll
                    for (int m = 0; m < 3; m++) {
                        uint32_t a[4];
                        ldsm4t(a, sb + OFF_RING + n * CH_BYTES + voff[m] + ks * (48 * 128));
                        mma_bf16(qa[m], a, xb[2 * ks], xb[2 * ks + 1]);
                    }
                __syncwarp();
                if (lane == 0) mbar_arrive(bar_empty + 8 * n, 1);
            }
            if (tid == 0) TS(11);
            const float a0 = t == 0 ? qa[0][0] : t == 1 ? qa[1][0] : qa[2][0];
            const float a1 = t == 0 ? qa[0][2] : t == 1 ? qa[1][2] : qa[2][2];
            if (t < 3) {
                uint32_t* qo = &box.q[par][j][48 * warp + 16 * t + g];
                st_box(qo, enc(a0));
                st_box(qo + 8, enc(a1));
            }
            if (warp < 3) {
                uint2 v[NSPLIT];
                wait_until(gtime_lo() + Q_DELAY);
                poll4(v, &box.q[par][0][2 * tid], DH);
                ((uint32_t*)(sp + OFF_Q))[tid] = pack_bf2((dec(v[0].x) + dec(v[1].x)) + (dec(v[2].x) + dec(v[3].x)),
                                                          (dec(v[0].y) + dec(v[1].y)) + (dec(v[2].y) + dec(v[3].y)));
            }
            bar_sync(4, 160);
        }
        if (tid == 0) TS(2);
        float* sS = (float*)(sp + OFF_S);
        float* sRed = (float*)(sp + OFF_RED);
        const float SC = 0.07216878364870322f * 1.4426950408889634f;
        float mx = -INFINITY;
        {
            uint32_t qb[12][2];
#pragma unroll
            for (int ks = 0; ks < 12; ks++) {
                qb[ks][0] = *(const uint32_t*)(sp + OFF_Q + (ks * 16 + 2 * t) * 2);
                qb[ks][1] = *(const uint32_t*)(sp + OFF_Q + (ks * 16 + 8 + 2 * t) * 2);
            }
            uint32_t koff[3];
            {
                const int r = 16 * (warp & 1) + (lane & 7) + ((lane >> 3) & 1) * 8, hi = lane >> 4;
#pragma unroll
                for (int c = 0; c < 3; c++) koff[c] = (3 * r + c) * 128 + ((hi ^ ((3 * r + c) & 7)) << 4);
            }
            const int spos = (g >> 1) * 8 + (warp & 1) * 4 + (g & 1);
#pragma unroll 1
            for (int n = warp >> 1; n < NCH; n += 2) {
                const int s = (N_K + n) & (NSLOT - 1);
                const uint32_t slot = sb + OFF_RING + s * CH_BYTES;
                mbar_wait(bar_full + 8 * s, ((N_K + n) / NSLOT) & 1);
                if (lane == 0 && (warp & 1) == 0) TC(n);
                float acc[3][4];
#pragma unroll
                for (int c = 0; c < 3; c++) acc[c][0] = acc[c][1] = acc[c][2] = acc[c][3] = 0.f;
#pragma unroll
                for (int kk = 0; kk < 4; kk++)
#pragma unroll
                    for (int c = 0; c < 3; c++) {
                        uint32_t a[4];
                        ldsm4(a, slot + (koff[c] ^ (kk << 5)));
                        mma_bf16(acc[c], a, qb[c * 4 + kk][0], qb[c * 4 + kk][1]);
                    }
                __syncwarp();
                if (lane == 0) mbar_arrive(bar_empty + 8 * s, 2);
                const float s0 = acc[0][0] + acc[1][0] + acc[2][0], s1 = acc[0][2] + acc[1][2] + acc[2][2];
                if (t == 0) { sS[n * CH_KEYS + spos] = s0; sS[n * CH_KEYS + spos + 2] = s1; }
                mx = fmaxf(mx, fmaxf(s0, s1));
            }
        }
        if (tid == 0) TS(3);
        mx = fmaxf(mx, __shfl_xor_sync(~0u, mx, 4));
        mx = fmaxf(mx, __shfl_xor_sync(~0u, mx, 8));
        mx = fmaxf(mx, __shfl_xor_sync(~0u, mx, 16));
        if (lane == 0) sRed[warp] = mx;
        bar_sync(3, 128);
        const float ms = fmaxf(fmaxf(sRed[0], sRed[1]), fmaxf(sRed[2], sRed[3])) * SC;
        float lsum = 0.f;
#pragma unroll 1
        for (int item = tid; item < 256; item += 128) {
            uint4* pp = (uint4*)sS + item * 2;
            const float4 sa = *(const float4*)pp, sc = *(const float4*)(pp + 1);
            const float sv[8] = {sa.x, sa.y, sa.z, sa.w, sc.x, sc.y, sc.z, sc.w};
            uint32_t hi[4], lo[4];
#pragma unroll
            for (int e = 0; e < 4; e++) {
                const float p0 = exp2f(fmaf(sv[2 * e], SC, -ms)), p1 = exp2f(fmaf(sv[2 * e + 1], SC, -ms));
                lsum += p0 + p1;
                hi[e] = pack_bf2(p0, p1);
                lo[e] = pack_bf2(p0 - bf_lo(hi[e]), p1 - bf_hi(hi[e]));
            }
            pp[0] = make_uint4(hi[0], hi[1], hi[2], hi[3]);
            pp[1] = make_uint4(lo[0], lo[1], lo[2], lo[3]);
        }
#pragma unroll
        for (int o = 16; o > 0; o >>= 1) lsum += __shfl_xor_sync(~0u, lsum, o);
        if (lane == 0) sRed[4 + warp] = lsum;
        bar_sync(3, 128);
        if (tid == 0) st_box2(&box.ml[par][2 * j], enc(ms), enc((sRed[4] + sRed[5]) + (sRed[6] + sRed[7])));
        uint32_t* ob = &box.o[par][warp][j][16 * t + g];
        asm volatile("" : "+l"(ob));
        if (tid == 0) TS(4);
        float oacc[3][4];
#pragma unroll
        for (int m = 0; m < 3; m++) oacc[m][0] = oacc[m][1] = oacc[m][2] = oacc[m][3] = 0.f;
        const uint8_t* pbase = sp + OFF_S + t * 32 + (g & 1) * 16;
#pragma unroll 1
        for (int i = 0; i < NCH; i++) {
            const int s = (N_V + i) & (NSLOT - 1);
            const uint32_t slot = sb + OFF_RING + s * CH_BYTES;
            const uint4 pa = *(const uint4*)(pbase + i * 128);
            mbar_wait(bar_full + 8 * s, ((N_V + i) / NSLOT) & 1);
            if (tid == 96) TC(NCH + i);
#pragma unroll
            for (int ks = 0; ks < 2; ks++)
#pragma unroll
                for (int m = 0; m < 3; m++) {
                    uint32_t a[4];
                    ldsm4t(a, slot + voff[m] + ks * (48 * 128));
                    mma_bf16(oacc[m], a, ks ? pa.z : pa.x, ks ? pa.w : pa.y);
                }
            __syncwarp();
            if (lane == 0) mbar_arrive(bar_empty + 8 * s, 1);
        }
        if (tid == 0) TS(5);
        const float a0 = t == 0 ? oacc[0][0] + oacc[0][1] : t == 1 ? oacc[1][0] + oacc[1][1] : oacc[2][0] + oacc[2][1];
        const float a1 = t == 0 ? oacc[0][2] + oacc[0][3] : t == 1 ? oacc[1][2] + oacc[1][3] : oacc[2][2] + oacc[2][3];
        if (t < 3) {
            st_box(ob, enc(a0));
            st_box(ob + 8, enc(a1));
        }
        if (lane == 0) mbar_arrive(bar_sent, 1);
    } else {
        const int bw = warp - 4;
        uint32_t abase = sb + OFF_RING + ((N_WO & (NSLOT - 1)) + (lane >> 4)) * CH_BYTES + (lane & 7) * 128 +
                         ((((2 * bw + ((lane >> 3) & 1)) ^ lane) & 7) << 4);
        uint32_t abase8 = abase - (lane >> 4) * (CH_BYTES - 1024);
        uint32_t oaddr = sb + OFF_O + t * 4;
        float4* accp = &acc[bw * 16 + (lane >> 1)][par][lane & 1];
        __nv_bfloat16* outp = out + 8 * (2 * bw + (t & 1) + 8 * (t >> 1)) + g;
        int tt = t;
        asm volatile("" : "+r"(abase), "+r"(abase8), "+r"(oaddr), "+l"(accp), "+l"(outp), "+r"(tt));
        uint32_t a[2][10][4], b[6];
        float y[10][4];
#pragma unroll
        for (int ks = 0; ks < 2; ks++) {
            mbar_wait(bar_wo + 16 * ks, 0);
            if (tid == 160) TC(2 * NCH + 2 * ks);
            mbar_wait(bar_wo + 16 * ks + 8, 0);
            if (tid == 160) TC(2 * NCH + 2 * ks + 1);
#pragma unroll
            for (int m = 0; m < 10; m++) ldsm4t(a[ks][m], abase + 2 * ks * CH_BYTES + m * 1024);
        }
        mbar_wait(bar_o, 0);
#pragma unroll
        for (int u = 0; u < 6; u++) asm volatile("ld.shared.u32 %0, [%1];" : "=r"(b[u]) : "r"(oaddr + u * 16) : "memory");
#pragma unroll
        for (int m = 0; m < 10; m++) y[m][0] = y[m][1] = y[m][2] = y[m][3] = 0.f;
#pragma unroll
        for (int ks = 0; ks < 2; ks++)
#pragma unroll
            for (int m = 0; m < 10; m++) mma_bf16(y[m], a[ks][m], b[2 * ks], b[2 * ks + 1]);
#pragma unroll
        for (int u = 0; u < 2; u++) {
            mbar_wait(bar_wo + 32 + 8 * u, 0);
            if (tid == 160) TC(2 * NCH + 4 + u);
            if (u == 1 && tid == 128) TS(12);
#pragma unroll
            for (int i = 0; i < 5; i++) ldsm4t(a[u][i], abase8 + (4 + u) * CH_BYTES + i * 2048);
#pragma unroll
            for (int i = 0; i < 5; i++) {
                mma_bf16_k8(y[2 * i], a[u][i][0], a[u][i][1], b[4 + u]);
                mma_bf16_k8(y[2 * i + 1], a[u][i][2], a[u][i][3], b[4 + u]);
            }
        }
        if (tid == 128) TS(7);
        float v[5];
#pragma unroll
        for (int k = 0; k < 5; k++) {
            const float lo = (tt & 1) ? y[2 * k][2] : y[2 * k][0], hi = (tt & 1) ? y[2 * k + 1][2] : y[2 * k + 1][0];
            v[k] = (tt & 2) ? hi : lo;
        }
        float4 e, f;
        asm volatile("atom.relaxed.gpu.global.add.v4.f32 {%0,%1,%2,%3}, [%4], {%5,%6,%7,%8};"
                     : "=f"(e.x), "=f"(e.y), "=f"(e.z), "=f"(e.w) : "l"(accp), "f"(v[0]), "f"(v[1]), "f"(v[2]), "f"(1.f) : "memory");
        asm volatile("atom.relaxed.gpu.global.add.v4.f32 {%0,%1,%2,%3}, [%4], {%5,%6,%7,%8};"
                     : "=f"(f.x), "=f"(f.y), "=f"(f.z), "=f"(f.w) : "l"(accp + 64 * 16), "f"(v[3]), "f"(v[4]), "f"(0.f), "f"(1.f) : "memory");
        if (e.w == (float)(NCTA - 1)) {
            st_bf16(outp, e.x + v[0]);
            st_bf16(outp + 128, e.y + v[1]);
            st_bf16(outp + 256, e.z + v[2]);
        }
        if (f.w == (float)(NCTA - 1)) {
            st_bf16(outp + 384, f.x + v[3]);
            st_bf16(outp + 512, f.y + v[4]);
        }
        if (tid == 128) TS(8);
    }
    PROF_END();
}

typedef CUresult (*EncodeTiledFn)(CUtensorMap*, CUtensorMapDataType, cuuint32_t, void*, const cuuint64_t*, const cuuint64_t*,
                                  const cuuint32_t*, const cuuint32_t*, CUtensorMapInterleave, CUtensorMapSwizzle,
                                  CUtensorMapL2promotion, CUtensorMapFloatOOBfill);

void make_map_rows(EncodeTiledFn fn, CUtensorMap* m, void* base, int rows, int row_elems) {
    cuuint64_t dims[3] = {64, (cuuint64_t)row_elems / 64, (cuuint64_t)rows};
    cuuint64_t strides[2] = {128, (cuuint64_t)row_elems * 2};
    cuuint32_t box[3] = {64, 3, (cuuint32_t)CH_KEYS};
    cuuint32_t estr[3] = {1, 1, 1};
    fn(m, CU_TENSOR_MAP_DATA_TYPE_BFLOAT16, 3, base, dims, strides, box, estr, CU_TENSOR_MAP_INTERLEAVE_NONE,
       CU_TENSOR_MAP_SWIZZLE_128B, CU_TENSOR_MAP_L2_PROMOTION_NONE, CU_TENSOR_MAP_FLOAT_OOB_FILL_NONE);
}

void make_map_wo(EncodeTiledFn fn, CUtensorMap* m, void* base) {
    cuuint64_t dims[3] = {64, (cuuint64_t)NH * DH, D_MODEL / 64};
    cuuint64_t strides[2] = {D_MODEL * 2, 128};
    cuuint32_t box[3] = {64, 8, D_MODEL / 64};
    cuuint32_t estr[3] = {1, 1, 1};
    fn(m, CU_TENSOR_MAP_DATA_TYPE_BFLOAT16, 3, base, dims, strides, box, estr, CU_TENSOR_MAP_INTERLEAVE_NONE,
       CU_TENSOR_MAP_SWIZZLE_128B, CU_TENSOR_MAP_L2_PROMOTION_NONE, CU_TENSOR_MAP_FLOAT_OOB_FILL_NONE);
}

}

extern "C" void kernel_launch(void* const* d_in, const int* in_sizes, int n_in, void* d_out, int out_size) {
    (void)in_sizes; (void)n_in; (void)out_size;
    void* fnp = nullptr;
    cudaDriverEntryPointQueryResult qr;
    cudaGetDriverEntryPoint("cuTensorMapEncodeTiled", &fnp, cudaEnableDefault, &qr);
    CUtensorMap tmQ, tmK, tmV, tmW;
    make_map_rows((EncodeTiledFn)fnp, &tmQ, d_in[3], D_MODEL, NH * DH);
    make_map_rows((EncodeTiledFn)fnp, &tmK, d_in[1], NH * SK, DH);
    make_map_rows((EncodeTiledFn)fnp, &tmV, d_in[2], NH * SK, DH);
    make_map_wo((EncodeTiledFn)fnp, &tmW, d_in[4]);
    cudaFuncSetAttribute(fused_decode_kernel, cudaFuncAttributeMaxDynamicSharedMemorySize, SMEM_BYTES);
    int dev = 0, mem_khz = 0, bus_bits = 0;
    cudaGetDevice(&dev);
    cudaDeviceGetAttribute(&mem_khz, cudaDevAttrMemoryClockRate, dev);
    cudaDeviceGetAttribute(&bus_bits, cudaDevAttrGlobalMemoryBusWidth, dev);
    const double peak = 2.0 * mem_khz * 1e3 * bus_bits / 8.0;
    const uint32_t tau_ps = peak > 1e12 ? (uint32_t)((double)NCTA * CH_BYTES / (peak * PACE_EFF) * 1e12) : 0u;
    void *boxes = nullptr, *acc = nullptr;
    cudaGetSymbolAddress(&boxes, g_box);
    cudaGetSymbolAddress(&acc, g_acc);
    fused_decode_kernel<<<NCTA, NTHREADS, SMEM_BYTES>>>(tmQ, tmK, tmV, tmW, (const __nv_bfloat16*)d_in[0],
                                                         (const __nv_bfloat16*)d_in[3], (__nv_bfloat16*)d_out,
                                                         (HeadBox*)boxes, (float4 (*)[2][8])acc, tau_ps);
}
```
